```python
import torch

def _softmax(x, axis=-1):
    return torch.softmax(x, dim=axis)
def _gelu(x):
    return torch.nn.functional.gelu(x, approximate="tanh")
def _silu(x):
    return torch.nn.functional.silu(x)
def _sigmoid(x):
    return torch.sigmoid(x)
def _layernorm(x, axis=-1, eps=1e-5):
    m = x.mean(dim=axis, keepdim=True)
    v = x.var(dim=axis, keepdim=True, unbiased=False)
    return (x - m) / torch.sqrt(v + eps)
def _scatter_add(tgt, idx, src, axis=0):
    return tgt.clone().index_add_(axis, idx, src)
def _segment_sum(src, seg, n):
    out = torch.zeros((n,) + src.shape[1:], dtype=src.dtype)
    return out.index_add_(0, seg, src)
def _pad(x, pw):
    flat = tuple(v for pair in reversed(pw) for v in pair)
    return torch.nn.functional.pad(x, flat)

kernel_name = 'gated_mix__gqa_block_cached__glu_gated_glu__decode'

def setup_inputs():

    _w = (lambda a: (lambda t: t.to(torch.bfloat16) if t.is_floating_point() else t)(torch.as_tensor(a)))
    def _A_setup():
        B, Sq, D = 4, 1, 512
        Hq, Hkv, Sk, Dh = 32, 8, 8192, 128
        assert Hq % Hkv == 0, (Hq, Hkv)
        return {
            "x": _w((lambda *s: torch.randn(*s, dtype=torch.bfloat16) * 0.05)(B, Sq, D)),
            "k_cache": _w((lambda *s: torch.randn(*s, dtype=torch.bfloat16) * 6.4)(B, Hkv, Sk, Dh)),
            "v_cache": _w((lambda *s: torch.randn(*s, dtype=torch.bfloat16) * 3.2)(B, Hkv, Sk, Dh)),
            "wq": _w((lambda *s: torch.randn(*s, dtype=torch.bfloat16) * 6.4)(D, Hq * Dh) * (D ** -0.5)),
            "wo": _w((lambda *s: torch.randn(*s, dtype=torch.bfloat16) * 3.2)(Hq * Dh, D) * ((Hq * Dh) ** -0.5)),
        }
    _A_in = _A_setup()

    def _B_setup():
        B, S, D, F = 4, 1, 512, 1792
        return {
            "x": _w((lambda *s: torch.randn(*s, dtype=torch.bfloat16) * 0.05)(B, S, D)),
            "w_gate": _w((lambda *s: torch.randn(*s, dtype=torch.bfloat16) * 3.2)(D, F)),
            "w_up": _w((lambda *s: torch.randn(*s, dtype=torch.bfloat16) * 0.2)(D, F)),
            "w_down": _w((lambda *s: torch.randn(*s, dtype=torch.bfloat16) * 0.2)(F, D)),
        }
    _B_in = _B_setup()

    return {
        "A_x": _A_in["x"],
        "A_k_cache": _A_in["k_cache"],
        "A_v_cache": _A_in["v_cache"],
        "A_wq": _A_in["wq"],
        "A_wo": _A_in["wo"],
        "B_x": _B_in["x"],
        "B_w_gate": _B_in["w_gate"],
        "B_w_up": _B_in["w_up"],
        "B_w_down": _B_in["w_down"],
        "gate_w": _w((lambda *s: torch.randn(*s, dtype=torch.bfloat16) * 0.05)(512) * 16.0),
    }

def reference(A_x, A_k_cache, A_v_cache, A_wq, A_wo, B_x, B_w_gate, B_w_up, B_w_down, gate_w):
    def _A_ref(x, k_cache, v_cache, wq, wo):
        B, Sq, D = x.shape
        Hq, Dh = 32, 128
        Hkv = k_cache.shape[1]
        rep = Hq // Hkv
        q = (lambda x, *d: x.permute(*d))((x @ wq).reshape(B, Sq, Hq, Dh), 0, 2, 1, 3)
        k = (lambda x, n, axis: torch.repeat_interleave(x, n, dim=axis))(k_cache, rep, axis=1)
        v = (lambda x, n, axis: torch.repeat_interleave(x, n, dim=axis))(v_cache, rep, axis=1)
        scores = torch.einsum("bhqd,bhkd->bhqk", q, k) * (Dh ** -0.5)
        p = _softmax(scores, axis=-1)
        o = torch.einsum("bhqk,bhkd->bhqd", p, v)
        return (lambda x, *d: x.permute(*d))(o, 0, 2, 1, 3).reshape(B, Sq, Hq * Dh) @ wo

    def _B_ref(x, w_gate, w_up, w_down):
        g = torch.einsum("bsd,df->bsf", x, w_gate)
        u = torch.einsum("bsd,df->bsf", x, w_up)
        h = _sigmoid(g) * u
        return torch.einsum("bsf,fd->bsd", h, w_down)

    x = A_x
    g = _sigmoid((x * gate_w).sum(-1, keepdims=True))
    a = _A_ref(x, A_k_cache, A_v_cache, A_wq, A_wo)
    b = _B_ref(x, B_w_gate, B_w_up, B_w_down)
    return g * a + (1 - g) * b
```

```cpp
#include <cuda_runtime.h>
#include <cuda_bf16.h>
#include <cuda.h>
#include <stdint.h>

namespace {

constexpr int NCTA      = 128;
constexpr int NTHREADS  = 448;
constexpr int SLOT      = 16384;
constexpr int NS        = 12;
constexpr int G         = 64;
constexpr int NG        = 128 / G;
constexpr int TP        = 128 / G;
constexpr int TPG       = TP / 2;
constexpr int NPH       = G / 4;
constexpr int REH       = 9;
constexpr int WIN0      = 4;
constexpr int NGLU      = 112;
constexpr int WIN       = 5;
constexpr int TAU       = 642;
constexpr int TAU0      = 1790;
constexpr int STAG      = 300;
constexpr int PAUSE_GAP = 1400;
constexpr int PAUSE_THR = 700;
constexpr int PAUSE_CAP = 1200;
constexpr int PAUSE_SUS = 1250;
constexpr int PAUSE_VOTES = 44;
constexpr float L2E     = 1.4426950408889634f;
constexpr int SPIN_LIMIT = 1 << 18;
static_assert(TP >= 2 && WIN0 - 2 <= TP, "layout");

constexpr int OFF_RED   = NS * SLOT;
constexpr int OFF_PB    = OFF_RED;
constexpr int PB_BYTES  = (2 * TP * 1024 > 4096) ? 2 * TP * 1024 : 4096;
constexpr int OFF_RED2  = OFF_RED + PB_BYTES;
constexpr int OFF_XS    = OFF_RED2 + 4096;
constexpr int OFF_QS    = OFF_XS + 4 * 520 * 2;
constexpr int OFF_MB    = OFF_QS + NPH * 4 * 136 * 2;
constexpr int OFF_LB    = OFF_MB + 256;
constexpr int OFF_PART  = OFF_LB + 128;
constexpr int OFF_OS    = OFF_PART + 512;
constexpr int OFF_HS    = OFF_OS + 256;
constexpr int OFF_GATE  = OFF_HS + 192;
constexpr int OFF_FIN   = OFF_GATE + 32;
constexpr int OFF_WB    = OFF_FIN + 512;
constexpr int OFF_SELP  = OFF_WB + G * 8;
constexpr int OFF_BAR   = OFF_SELP + 512;
constexpr int OFF_QBAR  = OFF_BAR + 2 * NS * 8;
constexpr int OFF_TAG   = OFF_QBAR + NPH * 8;
constexpr int OFF_CNT   = OFF_TAG + 4;
constexpr int OFF_SHIFT = OFF_TAG + 12;
constexpr int OFF_SEL   = OFF_TAG + 16;
constexpr int OFF_SUS   = OFF_SEL + 8;
constexpr int SMEM_USED = OFF_SEL + 16;
constexpr int SMEM_BYTES = SMEM_USED + 1024;
static_assert(SMEM_BYTES <= 232448, "smem");

__device__ unsigned int g_epoch;
__device__ __align__(256) unsigned int g_q[4 * 4096];
__device__ __align__(256) float g_po[32 * 16 * G * 32];
__device__ __align__(256) float g_ml[32 * G * 8];
constexpr int XF_STRIDE = (G >= 32 ? G / 32 : 1) * 2048;
constexpr int X_PF = 0;
constexpr int X_MF = X_PF + NG * 16 * XF_STRIDE;
constexpr int X_P2 = X_MF + NG * 16 * 2048;
constexpr int X_END = X_P2 + NCTA * 4096;
__device__ __align__(256) float g_x[X_END + 2048];
__device__ __align__(256) unsigned long long g_pause[2 * 32];
__device__ __align__(256) unsigned int g_sel[NCTA * 8];


__device__ __forceinline__ uint32_t smem_u32(const void* p) { return (uint32_t)__cvta_generic_to_shared(p); }
__device__ __forceinline__ void mbar_init(uint32_t bar, uint32_t cnt) {
    asm volatile("mbarrier.init.shared::cta.b64 [%0], %1;" :: "r"(bar), "r"(cnt) : "memory");
}
__device__ __forceinline__ void mbar_expect_tx(uint32_t bar, uint32_t bytes) {
    asm volatile("mbarrier.arrive.expect_tx.shared::cta.b64 _, [%0], %1;" :: "r"(bar), "r"(bytes) : "memory");
}
__device__ __forceinline__ void mbar_arrive(uint32_t bar) {
    asm volatile("mbarrier.arrive.shared::cta.b64 _, [%0];" :: "r"(bar) : "memory");
}
__device__ __forceinline__ void mbar_arrive2(uint32_t bar) {
    asm volatile("mbarrier.arrive.shared::cta.b64 _, [%0], 2;" :: "r"(bar) : "memory");
}
__device__ __forceinline__ bool mbar_try(uint32_t bar, uint32_t parity) {
    uint32_t ok;
    asm volatile("{\n.reg .pred p;\nmbarrier.try_wait.parity.shared::cta.b64 p, [%1], %2;\nselp.u32 %0, 1, 0, p;\n}\n"
                 : "=r"(ok) : "r"(bar), "r"(parity) : "memory");
    return ok != 0;
}
__device__ __forceinline__ bool mbar_test(uint32_t bar, uint32_t parity) {
    uint32_t ok;
    asm volatile("{\n.reg .pred p;\nmbarrier.test_wait.parity.shared::cta.b64 p, [%1], %2;\nselp.u32 %0, 1, 0, p;\n}\n"
                 : "=r"(ok) : "r"(bar), "r"(parity) : "memory");
    return ok != 0;
}
__device__ __forceinline__ void mbar_wait(uint32_t bar, uint32_t parity) {
    int n = 0;
    while (!mbar_try(bar, parity) && ++n < SPIN_LIMIT) {}
}
__device__ __forceinline__ void mbar_spin(uint32_t bar, uint32_t parity, int lim) {
    for (int n = 0; !mbar_test(bar, parity) && n < lim; n++) {}
}
__device__ __forceinline__ void tma2d(uint32_t dst, const CUtensorMap* m, int c0, int c1, uint32_t bar) {
    asm volatile("cp.async.bulk.tensor.2d.shared::cluster.global.mbarrier::complete_tx::bytes [%0], [%1, {%3, %4}], [%2];"
                 :: "r"(dst), "l"(m), "r"(bar), "r"(c0), "r"(c1) : "memory");
}
__device__ __forceinline__ void tma3d(uint32_t dst, const CUtensorMap* m, int c0, int c1, int c2, uint32_t bar) {
    asm volatile("cp.async.bulk.tensor.3d.shared::cluster.global.mbarrier::complete_tx::bytes [%0], [%1, {%3, %4, %5}], [%2];"
                 :: "r"(dst), "l"(m), "r"(bar), "r"(c0), "r"(c1), "r"(c2) : "memory");
}
__device__ __forceinline__ void tma3d_hint(uint32_t dst, const CUtensorMap* m, int c0, int c1, int c2, uint32_t bar, uint64_t pol) {
    asm volatile("cp.async.bulk.tensor.3d.shared::cluster.global.mbarrier::complete_tx::bytes.L2::cache_hint [%0], [%1, {%3, %4, %5}], [%2], %6;"
                 :: "r"(dst), "l"(m), "r"(bar), "r"(c0), "r"(c1), "r"(c2), "l"(pol) : "memory");
}
__device__ __forceinline__ void prefetch_tmap(const CUtensorMap* m) {
    asm volatile("prefetch.tensormap [%0];" :: "l"(m) : "memory");
}
__device__ __forceinline__ void ldsm4(uint32_t (&r)[4], uint32_t addr) {
    asm volatile("ldmatrix.sync.aligned.m8n8.x4.shared.b16 {%0,%1,%2,%3}, [%4];"
                 : "=r"(r[0]), "=r"(r[1]), "=r"(r[2]), "=r"(r[3]) : "r"(addr) : "memory");
}
__device__ __forceinline__ void ldsm4t(uint32_t (&r)[4], uint32_t addr) {
    asm volatile("ldmatrix.sync.aligned.m8n8.x4.trans.shared.b16 {%0,%1,%2,%3}, [%4];"
                 : "=r"(r[0]), "=r"(r[1]), "=r"(r[2]), "=r"(r[3]) : "r"(addr) : "memory");
}
__device__ __forceinline__ void mma16816(float (&c)[4], const uint32_t (&a)[4], uint32_t b0, uint32_t b1) {
    asm volatile("mma.sync.aligned.m16n8k16.row.col.f32.bf16.bf16.f32 {%0,%1,%2,%3}, {%4,%5,%6,%7}, {%8,%9}, {%0,%1,%2,%3};"
                 : "+f"(c[0]), "+f"(c[1]), "+f"(c[2]), "+f"(c[3])
                 : "r"(a[0]), "r"(a[1]), "r"(a[2]), "r"(a[3]), "r"(b0), "r"(b1));
}
__device__ __forceinline__ uint32_t movmatrix_t(uint32_t a) {
    uint32_t d;
    asm volatile("movmatrix.sync.aligned.m8n8.trans.b16 %0, %1;" : "=r"(d) : "r"(a));
    return d;
}
__device__ __forceinline__ uint32_t pack_bf16(float lo, float hi) {
    uint32_t d;
    asm("cvt.rn.bf16x2.f32 %0, %1, %2;" : "=r"(d) : "f"(hi), "f"(lo));
    return d;
}
__device__ __forceinline__ float bf_lo(uint32_t v) { return __uint_as_float(v << 16); }
__device__ __forceinline__ float bf_hi(uint32_t v) { return __uint_as_float(v & 0xffff0000u); }
__device__ __forceinline__ float rbf(float v) { return bf_lo(pack_bf16(v, 0.f)); }
__device__ __forceinline__ float ex2(float x) { float y; asm("ex2.approx.ftz.f32 %0, %1;" : "=f"(y) : "f"(x)); return y; }
__device__ __forceinline__ float sigmoidf(float v) { return __fdividef(1.f, 1.f + __expf(-v)); }
__device__ __forceinline__ void bar_sync(int id, int n) { asm volatile("bar.sync %0, %1;" :: "r"(id), "r"(n) : "memory"); }
__device__ __forceinline__ void bar_arrive(int id, int n) { asm volatile("bar.arrive %0, %1;" :: "r"(id), "r"(n) : "memory"); }

__device__ __forceinline__ void st_rlx_u32(void* p, uint32_t v) {
    asm volatile("st.relaxed.gpu.global.u32 [%0], %1;" :: "l"(p), "r"(v) : "memory");
}
__device__ __forceinline__ void st_rlx_v4(void* p, uint32_t a, uint32_t b, uint32_t c, uint32_t d) {
    asm volatile("st.relaxed.gpu.global.v4.u32 [%0], {%1, %2, %3, %4};" :: "l"(p), "r"(a), "r"(b), "r"(c), "r"(d) : "memory");
}
__device__ __forceinline__ void st_rlx_v2_if(void* p, uint32_t a, uint32_t b, bool pred) {
    asm volatile("{\n.reg .pred p;\nsetp.ne.u32 p, %3, 0;\n@p st.relaxed.gpu.global.v2.u32 [%0], {%1, %2};\n}\n"
                 :: "l"(p), "r"(a), "r"(b), "r"((uint32_t)pred) : "memory");
}
__device__ __forceinline__ void st_rlx_v4_if(void* p, uint32_t a, uint32_t b, uint32_t c, uint32_t d, bool pred) {
    asm volatile("{\n.reg .pred p;\nsetp.ne.u32 p, %5, 0;\n@p st.relaxed.gpu.global.v4.u32 [%0], {%1, %2, %3, %4};\n}\n"
                 :: "l"(p), "r"(a), "r"(b), "r"(c), "r"(d), "r"((uint32_t)pred) : "memory");
}
__device__ __forceinline__ uint4 ld_rlx_v4(const void* p) {
    uint4 v;
    asm volatile("ld.relaxed.gpu.global.v4.u32 {%0, %1, %2, %3}, [%4];" : "=r"(v.x), "=r"(v.y), "=r"(v.z), "=r"(v.w) : "l"(p) : "memory");
    return v;
}
__device__ __forceinline__ void ld_rlx_v4_if(uint4& v, const void* p, bool pred) {
    asm volatile("{\n.reg .pred p;\nsetp.ne.u32 p, %5, 0;\n@p ld.relaxed.gpu.global.v4.u32 {%0, %1, %2, %3}, [%4];\n}\n"
                 : "+r"(v.x), "+r"(v.y), "+r"(v.z), "+r"(v.w) : "l"(p), "r"((uint32_t)pred) : "memory");
}
__device__ __forceinline__ uint32_t tagf(float v, uint32_t tag) { return (__float_as_uint(v) & ~3u) | tag; }
__device__ __forceinline__ float untag(uint32_t w) { return __uint_as_float(w & ~3u); }
__device__ __forceinline__ bool ok4(const uint4& v, uint32_t tag, uint32_t mask) {
    return (((v.x ^ tag) | (v.y ^ tag) | (v.z ^ tag) | (v.w ^ tag)) & mask) == 0;
}
__device__ __forceinline__ void wait_cnt(volatile int* cnt, int need, unsigned ns) {
    for (int n = 0; *cnt < need && n < SPIN_LIMIT; n++) __nanosleep(ns);
}

template <int N>
__device__ __forceinline__ int near_copy(const float* p, int stride, volatile int* sink) {
    uint4 a[N], b[N];
#pragma unroll
    for (int r = 0; r < N; r++) a[r] = ld_rlx_v4(p + r * stride);
#pragma unroll
    for (int r = 0; r < N; r++) b[r] = ld_rlx_v4(p + 1024 + r * stride);
    uint32_t xa = 0, xb = 0, ta, tb;
#pragma unroll
    for (int r = 0; r < N; r++) xa |= a[r].x;
    xa = __reduce_or_sync(0xffffffffu, xa);
    if (xa == 0xdeadbeefu) *sink = 1;
    asm volatile("mov.u32 %0, %clock;" : "=r"(ta) :: "memory");
#pragma unroll
    for (int r = 0; r < N; r++) xb |= b[r].x;
    xb = __reduce_or_sync(0xffffffffu, xb);
    if (xb == 0xdeadbeefu) *sink = 1;
    asm volatile("mov.u32 %0, %clock;" : "=r"(tb) :: "memory");
    return __shfl_sync(0xffffffffu, (int)(tb - ta < 130u), 0);
}

struct Maps {
    CUtensorMap k, v, wq, wg, wu, wo, wd;
};

__global__ void __launch_bounds__(NTHREADS, 1)
fused_decode_kernel(const __grid_constant__ Maps maps,
                    const __nv_bfloat16* __restrict__ x,
                    const __nv_bfloat16* __restrict__ gate_w,
                    const __nv_bfloat16* __restrict__ wq,
                    __nv_bfloat16* __restrict__ out, const int tau)
{
    uint32_t t0;
    asm volatile("{\n.reg .pred p;\n.reg .u32 t;\nmov.u32 t, %%tid.x;\nsetp.eq.u32 p, t, 256;\n"
                 "@p cp.async.bulk.prefetch.L2.global [%1], 32768;\nmov.u32 %0, %%globaltimer_lo;\n}\n"
                 : "=r"(t0) : "l"(wq + (size_t)blockIdx.x * 16384) : "memory");
    extern __shared__ unsigned char smem_raw[];
    const uint32_t sb = (smem_u32(smem_raw) + 1023u) & ~1023u;
    unsigned char* sg = smem_raw + (sb - smem_u32(smem_raw));

    const int tid = threadIdx.x, warp = tid >> 5, lane = tid & 31;
    const int c = blockIdx.x;
    const int grp = c / G, jj = c % G;
    const int hkv = c >> 4, j16 = c & 15;
    const bool has_glu = c < NGLU;
    constexpr int it_kv0 = 2, it_g = it_kv0 + 64, it_u = it_g + 1;
    const int it_tail = it_kv0 + (has_glu ? 66 : 64);
    const int nitems = it_tail + 4;
    const uint32_t bar_full = sb + OFF_BAR, bar_empty = sb + OFF_BAR + NS * 8;
    float* const xg = reinterpret_cast<float*>((reinterpret_cast<uintptr_t>(g_x) + 8191) & ~(uintptr_t)8191);
    volatile int* const cnt = reinterpret_cast<volatile int*>(sg + OFF_CNT);

    if (tid == 256) {
#pragma unroll
        for (int i = 0; i < NS; i++) { mbar_init(bar_full + i * 8, 1); mbar_init(bar_empty + i * 8, 8); }
        asm volatile("fence.mbarrier_init.release.cluster;" ::: "memory");
        asm volatile("fence.proxy.async.shared::cta;" ::: "memory");
        mbar_expect_tx(bar_full, SLOT);
        tma2d(sb, &maps.wq, c * 32, 0, bar_full);
        mbar_expect_tx(bar_full + 8, SLOT);
        tma2d(sb + SLOT, &maps.wq, c * 32, 256, bar_full + 8);
#pragma unroll
        for (int i = 0; i < NPH; i++) mbar_init(sb + OFF_QBAR + i * 8, 128);
        *reinterpret_cast<volatile int*>(sg + OFF_SHIFT) = 0;
        *reinterpret_cast<volatile int*>(sg + OFF_SUS) = 0;
    }

    if (warp == 8) {
        uint64_t pol = 0;
        if (lane == 0) {
            asm volatile("createpolicy.fractional.L2::evict_first.b64 %0, 1.0;" : "=l"(pol));
            for (int it = it_kv0; it < WIN0; it++) {
                mbar_expect_tx(bar_full + it * 8, SLOT);
                tma3d_hint(sb + it * SLOT, &maps.k, 0, grp * 8192 + ((it - it_kv0) * G + jj) * 64, 0, bar_full + it * 8, pol);
            }
            prefetch_tmap(&maps.v); prefetch_tmap(&maps.wg); prefetch_tmap(&maps.wu); prefetch_tmap(&maps.wo); prefetch_tmap(&maps.wd);
        }
        __syncwarp();
        bar_arrive(9, NTHREADS);
        if (lane == 0) {
            uint32_t sbo;
            asm volatile("mov.u32 %0, %1;" : "=r"(sbo) : "r"(sb));
            const uint32_t tb = t0 + TAU0 - WIN0 * tau + jj * STAG / G;
            int nl = 0, shift = 0, base = 0, arm = 0, slot = WIN0;
            bool voted = false;
            uint32_t tp = 0, par = 1;
            uint32_t lbar = sbo + OFF_BAR, lpar = 0, lnom = tb;
#pragma unroll 1
            for (int it = WIN0; it < nitems; it++) {
                const uint32_t dst = sbo + slot * SLOT, bar = sbo + OFF_BAR + slot * 8;
                if (it >= NS) mbar_wait(bar + NS * 8, par);
                if (++slot == NS) { slot = 0; par ^= 1; }
                const bool tail = it >= it_tail;
                const int n = it - it_kv0, B = n / TP;
                const bool isv = B == 2 * NPH - 1 || (B > 0 && !(B & 1));
                const int ph = B == 2 * NPH - 1 ? NPH - 1 : (isv ? B / 2 - 1 : (B + 1) / 2);
                const int row = (ph * NG + grp) * 8192 + ((n % TP) * G + jj) * 64;
                const CUtensorMap* kvm = isv ? &maps.v : &maps.k;
                mbar_expect_tx(bar, tail ? (has_glu ? 12288 : 8192) : SLOT);
                const uint32_t due = tb + it * tau + (tail ? 120 - (it - it_tail) * ((tau * 5) >> 4) : 0);
                for (int q = 0; q < SPIN_LIMIT; q++) {
                    uint32_t tn;
                    asm volatile("mov.u32 %0, %globaltimer_lo;" : "=r"(tn));
                    if (nl < it && mbar_test(lbar, lpar)) {
                        const int off = (int)(tn - lnom);
                        if (nl <= 6) base = off;
                        else {
                            if (shift == 0 && !voted) {
                                const int e = off - base;
                                if ((int)(tn - tp) > PAUSE_GAP) arm = nl + 1;
                                if (e > PAUSE_THR && nl <= arm) {
                                    const unsigned ep = *reinterpret_cast<volatile unsigned int*>(sg + OFF_TAG);
                                    asm volatile("red.relaxed.gpu.global.add.u64 [%0], %1;"
                                                 :: "l"(&g_pause[(ep & 1) * 32]), "l"((1ull << 32) | (unsigned)min(e, PAUSE_CAP)) : "memory");
                                    voted = true;
                                } else {
                                    base += e >> 3;
                                }
                            }
                            if ((int)(tn - tp) > PAUSE_SUS) asm volatile("st.volatile.shared.u32 [%0], %1;" :: "r"(sbo + OFF_SUS), "r"(nl) : "memory");
                        }
                        tp = tn;
                        nl++;
                        lnom += tau;
                        lbar += 8;
                        if (lbar == sbo + OFF_BAR + NS * 8) { lbar = sbo + OFF_BAR; lpar ^= 1; }
                    }
                    if (nl > it - WIN && (int)(tn - due) >= shift) break;
                    asm volatile("ld.volatile.shared.u32 %0, [%1];" : "=r"(shift) : "r"(sbo + OFF_SHIFT) : "memory");
                }
                if (it < it_g) {
                    tma3d_hint(dst, kvm, 0, row, 0, bar, pol);
                } else if (tail) {
                    const int cg = ((it - it_tail + (c >> 5)) & 3) * 2, wr = (hkv * 4 + 2 * (j16 >> 3)) * 128 + (j16 & 7) * 16;
                    tma3d(dst, &maps.wo, 0, wr, cg, bar);
                    tma3d(dst + 4096, &maps.wo, 0, wr + 128, cg, bar);
                    if (has_glu) tma3d(dst + 8192, &maps.wd, 0, c * 16, cg, bar);
                } else {
                    const CUtensorMap* m = (it == it_g) ? &maps.wg : &maps.wu;
                    tma2d(dst, m, c * 16, 0, bar);
                    tma2d(dst + 8192, m, c * 16, 256, bar);
                }
            }
        }
        return;
    }

    if (warp == 13) {
        bar_sync(9, NTHREADS);
        const uint32_t ep = *reinterpret_cast<volatile unsigned int*>(sg + OFF_TAG), tag = ep % 3u + 1u;
        if (lane < 8) st_rlx_u32(&g_sel[c * 8 + lane], 0u);
        if (c == 0 && lane == 0)
            asm volatile("st.relaxed.gpu.global.u64 [%0], %1;" :: "l"(&g_pause[(~ep & 1) * 32]), "l"(0ull) : "memory");
        int sus = 0, left = 0;
        auto look = [&]() {
            __nanosleep(300);
            const int s = *reinterpret_cast<volatile int*>(sg + OFF_SUS);
            if (s != sus) { sus = s; left = 8; }
            if (left > 0 && *reinterpret_cast<volatile int*>(sg + OFF_SHIFT) == 0) {
                left--;
                unsigned long long v;
                asm volatile("ld.relaxed.gpu.global.u64 %0, [%1];" : "=l"(v) : "l"(&g_pause[(ep & 1) * 32]) : "memory");
                if ((int)(v >> 32) >= PAUSE_VOTES && lane == 0)
                    *reinterpret_cast<volatile int*>(sg + OFF_SHIFT) = (int)((uint32_t)v / (uint32_t)(v >> 32)) + 200;
                __syncwarp();
            }
        };
        auto watch = [&](int until) { for (int n = 0; *cnt < until && n < SPIN_LIMIT; n++) look(); };
        watch(REH + 1);
        float* reg = xg + X_P2 + c * 4096;
        const int s0 = near_copy<1>(reg + ((c & 7) + 8 * (lane >> 2)) * 16 + (lane & 3) * 4, 0, cnt + 1);
        const int s1 = near_copy<1>(reg + 2048 + ((c & 7) + 8 * (lane >> 2)) * 16 + (lane & 3) * 4, 0, cnt + 1);
#pragma unroll
        for (int r = 0; r < 8; r++) {
            st_rlx_v4(reg + s0 * 1024 + r * 128 + lane * 4, 0u, 0u, 0u, 0u);
            st_rlx_v4(reg + 2048 + s1 * 1024 + r * 128 + lane * 4, 0u, 0u, 0u, 0u);
        }
        __threadfence();
        __syncwarp();
        if (lane < 8) st_rlx_u32(&g_sel[c * 8 + lane], (uint32_t)(s1 << 3 | s0 << 2) | tag);
        if (lane < 2) reinterpret_cast<volatile int*>(sg + OFF_SEL)[lane] = lane ? s1 : s0;
        uint4 v = make_uint4(0u, 0u, 0u, 0u);
        watch(REH + 4);
        for (int n = 0; n < SPIN_LIMIT; n++) {
            if (!ok4(v, tag, 3u)) {
                asm volatile("ld.relaxed.gpu.global.u32 %0, [%4]; ld.relaxed.gpu.global.u32 %1, [%4 + 1024];"
                             "ld.relaxed.gpu.global.u32 %2, [%4 + 2048]; ld.relaxed.gpu.global.u32 %3, [%4 + 3072];"
                             : "=r"(v.x), "=r"(v.y), "=r"(v.z), "=r"(v.w) : "l"(g_sel + lane * 8) : "memory");
            }
            __syncwarp();
            if (__all_sync(0xffffffffu, ok4(v, tag, 3u))) break;
            look();
            look();
        }
        __threadfence();
        uint32_t* sp = reinterpret_cast<uint32_t*>(sg + OFF_SELP) + lane;
        const int sh = 8 - (c >> 6);
        sp[0] = v.x << sh; sp[32] = v.y << sh; sp[64] = v.z << sh; sp[96] = v.w << sh;
        bar_arrive(5, 320);
        watch(NPH + 1);
        return;
    }

    if (warp > 8) {
        bar_sync(9, NTHREADS);
        const uint32_t tag = *reinterpret_cast<volatile unsigned int*>(sg + OFF_TAG) % 3u + 1u;
        const int hw = warp - 9, mi = lane >> 3, l7 = lane & 7;
        {
            const int ht = tid - 288;
            auto q_src = [&](int ph) { const int P = ph * NG + grp; return g_q + (P >> 3) * 4096 + (P & 7) * 512 + ht * 4; };
            constexpr int QB = 4;
#pragma unroll 1
            for (int p0 = 0; p0 < NPH; p0 += QB) {
                wait_cnt(cnt, p0 / QB, p0 ? 200 : 50);
                uint4 u[QB];
#pragma unroll
                for (int r = 0; r < QB; r++) u[r] = ld_rlx_v4(q_src(p0 + r));
#pragma unroll
                for (int r = 0; r < QB; r++) {
                    for (int m = 0; m < SPIN_LIMIT; m++) {
                        const bool bad = !ok4(u[r], tag, 0xffffu);
                        if (!__any_sync(0xffffffffu, bad)) break;
                        ld_rlx_v4_if(u[r], q_src(p0 + r), bad);
                        if (r + 1 < QB) ld_rlx_v4_if(u[r + 1 < QB ? r + 1 : r], q_src(p0 + r + 1), !ok4(u[r + 1 < QB ? r + 1 : r], tag, 0xffffu));
                    }
                    *reinterpret_cast<uint2*>(sg + OFF_QS + (((p0 + r) * 4 + hw) * 136 + lane * 4) * 2) =
                        make_uint2(__byte_perm(u[r].x, u[r].y, 0x7632), __byte_perm(u[r].z, u[r].w, 0x7632));
                    mbar_arrive(sb + OFF_QBAR + (p0 + r) * 8);
                }
            }
        }
#pragma unroll 1
        for (int b = 0; b < 4; b++) {
            const int Pg = b * 8 + hkv, gp = Pg / NG;
            const bool fin = gp == NPH - 1;
            constexpr int KM = (G + 31) / 32, NR = G / 16;
            const int pj0 = hw * (G / 4) + mi;
            const float* src = g_po + ((size_t)(Pg * 16 + j16) * G + pj0) * 32 + l7 * 4;
            const float* msrc = g_ml + (Pg * G + (lane % G)) * 8 + (j16 >> 3) * 4;
            if (fin) {
                wait_cnt(cnt, REH + 2, 100);
                const int cf = (hkv & (NG - 1)) * 16 + j16;
                src = xg + X_PF + cf * XF_STRIDE + (pj0 >> 5) * 2048 + (pj0 & 31) * 32 + l7 * 4;
                msrc = xg + X_MF + cf * 2048 + (lane % G) * 8;
                src += near_copy<NR>(src, 128, cnt + 1) * 1024;
                if (hw == 3) msrc += near_copy<KM>(msrc, 256, cnt + 1) * 1024;
            }
            wait_cnt(cnt, fin ? NPH - 1 : gp + 2, 64);
            uint4 v[NR];
#pragma unroll
            for (int r = 0; r < NR; r++) {
                v[r] = make_uint4(0u, 0u, 0u, 0u);
                ld_rlx_v4_if(v[r], src + r * 128, !fin);
            }
            if (hw == 3) {
                float mA[KM], lA[KM], mB[KM], lB[KM];
                uint4 u[KM];
#pragma unroll
                for (int k = 0; k < KM; k++) u[k] = ld_rlx_v4(msrc + k * 256);
                for (int n = 0; n < SPIN_LIMIT; n++) {
                    bool ok = true;
#pragma unroll
                    for (int k = 0; k < KM; k++) ok = ok && ok4(u[k], tag, 3u);
                    if (__all_sync(0xffffffffu, ok)) break;
                    __nanosleep(100);
#pragma unroll
                    for (int k = 0; k < KM; k++) ld_rlx_v4_if(u[k], msrc + k * 256, !ok4(u[k], tag, 3u));
                }
#pragma unroll
                for (int k = 0; k < KM; k++) {
                    mA[k] = untag(u[k].x); lA[k] = untag(u[k].y);
                    mB[k] = untag(u[k].z); lB[k] = untag(u[k].w);
                }
                float MA = mA[0], MB = mB[0];
#pragma unroll
                for (int k = 1; k < KM; k++) { MA = fmaxf(MA, mA[k]); MB = fmaxf(MB, mB[k]); }
#pragma unroll
                for (int o = (G >= 32 ? 16 : 8); o > 0; o >>= 1) {
                    MA = fmaxf(MA, __shfl_xor_sync(0xffffffffu, MA, o));
                    MB = fmaxf(MB, __shfl_xor_sync(0xffffffffu, MB, o));
                }
                float LA = 0.f, LB = 0.f;
#pragma unroll
                for (int k = 0; k < KM; k++) {
                    mA[k] = ex2((mA[k] - MA) * L2E); mB[k] = ex2((mB[k] - MB) * L2E);
                    LA += mA[k] * lA[k]; LB += mB[k] * lB[k];
                }
#pragma unroll
                for (int o = (G >= 32 ? 16 : 8); o > 0; o >>= 1) {
                    LA += __shfl_xor_sync(0xffffffffu, LA, o);
                    LB += __shfl_xor_sync(0xffffffffu, LB, o);
                }
                LA = __fdividef(1.f, LA); LB = __fdividef(1.f, LB);
#pragma unroll
                for (int k = 0; k < KM; k++)
                    if (lane + 32 * k < G) reinterpret_cast<float2*>(sg + OFF_WB)[lane + 32 * k] = make_float2(mA[k] * LA, mB[k] * LB);
            }
            bar_sync(8, 128);
            float w0[NR], w1[NR];
#pragma unroll
            for (int r = 0; r < NR; r++) {
                const float2 w = reinterpret_cast<const float2*>(sg + OFF_WB)[pj0 + 4 * r];
                w0[r] = w.x; w1[r] = w.y;
            }
            if (fin) { for (int n = 0; *cnt <= NPH && n < SPIN_LIMIT; n++) {} }
            for (int n = 0; n < SPIN_LIMIT; n++) {
                bool ok = true;
#pragma unroll
                for (int r = 0; r < NR; r++) ok = ok && ok4(v[r], tag, 3u);
                if (__all_sync(0xffffffffu, ok)) break;
                if (!fin) __nanosleep(64);
#pragma unroll
                for (int r = 0; r < NR; r++) ld_rlx_v4_if(v[r], src + r * 128, !ok4(v[r], tag, 3u));
            }
            float o0 = 0.f, o1 = 0.f, o2 = 0.f, o3 = 0.f;
#pragma unroll
            for (int r = 0; r < NR; r++) {
                o0 += w0[r] * untag(v[r].x); o1 += w1[r] * untag(v[r].y);
                o2 += w0[r] * untag(v[r].z); o3 += w1[r] * untag(v[r].w);
            }
#pragma unroll
            for (int o = 8; o <= 16; o <<= 1) {
                o0 += __shfl_xor_sync(0xffffffffu, o0, o); o1 += __shfl_xor_sync(0xffffffffu, o1, o);
                o2 += __shfl_xor_sync(0xffffffffu, o2, o); o3 += __shfl_xor_sync(0xffffffffu, o3, o);
            }
            if (lane < 8) reinterpret_cast<float4*>(sg + OFF_PART)[hw * 8 + lane] = make_float4(o0, o1, o2, o3);
            if (hw == 0) {
                bar_sync(6, 128);
                float4 s = reinterpret_cast<const float4*>(sg + OFF_PART)[lane];
#pragma unroll
                for (int o = 8; o <= 16; o <<= 1) {
                    s.x += __shfl_xor_sync(0xffffffffu, s.x, o); s.y += __shfl_xor_sync(0xffffffffu, s.y, o);
                    s.z += __shfl_xor_sync(0xffffffffu, s.z, o); s.w += __shfl_xor_sync(0xffffffffu, s.w, o);
                }
                const uint32_t px = pack_bf16(s.x, s.y), pz = pack_bf16(s.z, s.w);
                const uint32_t xb = __shfl_down_sync(0xffffffffu, px, 1), zb = __shfl_down_sync(0xffffffffu, pz, 1);
                if (lane < 8 && !(lane & 1))
                    reinterpret_cast<uint4*>(sg + OFF_OS)[b * 4 + (lane >> 1)] =
                        make_uint4(__byte_perm(px, xb, 0x5410), __byte_perm(pz, zb, 0x5410), __byte_perm(px, xb, 0x7632), __byte_perm(pz, zb, 0x7632));
            } else {
                bar_arrive(6, 128);
            }
            if (b < 3) bar_sync(7, 128);
        }
        if (hw == 0) bar_arrive(5, 320);
        return;
    }

    const int g = lane >> 2, t4 = lane & 3;
    const int mi = lane >> 3, l7 = lane & 7;
    __nv_bfloat16* xs = reinterpret_cast<__nv_bfloat16*>(sg + OFF_XS);
    float* red = reinterpret_cast<float*>(sg + OFF_RED);
    float* gates = reinterpret_cast<float*>(sg + OFF_GATE);

    uint4 gw0 = make_uint4(0, 0, 0, 0), gw1 = gw0;
    {
        const uint4 xv = __ldg(reinterpret_cast<const uint4*>(x) + tid);
        if (warp < 4) {
            gw0 = __ldg(reinterpret_cast<const uint4*>(gate_w) + lane * 2);
            gw1 = __ldg(reinterpret_cast<const uint4*>(gate_w) + lane * 2 + 1);
            st_rlx_u32(&g_q[warp * 4096 + c * 32 + lane], 0u);
        }
        if (tid == 255) {
            unsigned int e;
            asm volatile("ld.relaxed.gpu.global.u32 %0, [%1];" : "=r"(e) : "l"(&g_epoch) : "memory");
            *reinterpret_cast<volatile unsigned int*>(sg + OFF_TAG) = e;
            *cnt = -1;
        }
        *reinterpret_cast<uint4*>(xs + (tid >> 6) * 520 + (tid & 63) * 8) = xv;
    }
    bar_sync(9, NTHREADS);
    const unsigned int epoch = *reinterpret_cast<volatile unsigned int*>(sg + OFF_TAG);
    const uint32_t tag = epoch % 3u + 1u;

    if (warp < 4) {
        const uint4 xa = *reinterpret_cast<const uint4*>(xs + warp * 520 + lane * 16);
        const uint4 xb = *reinterpret_cast<const uint4*>(xs + warp * 520 + lane * 16 + 8);
        const uint32_t xw[8] = {xa.x, xa.y, xa.z, xa.w, xb.x, xb.y, xb.z, xb.w};
        const uint32_t ww[8] = {gw0.x, gw0.y, gw0.z, gw0.w, gw1.x, gw1.y, gw1.z, gw1.w};
        float s = 0.f;
#pragma unroll
        for (int i = 0; i < 8; i++) {
            const uint32_t p = pack_bf16(bf_lo(xw[i]) * bf_lo(ww[i]), bf_hi(xw[i]) * bf_hi(ww[i]));
            s += bf_lo(p) + bf_hi(p);
        }
#pragma unroll
        for (int o = 16; o > 0; o >>= 1) s += __shfl_xor_sync(0xffffffffu, s, o);
        if (lane == 0) {
            const float gt = rbf(sigmoidf(rbf(s)));
            gates[warp] = gt;
            gates[4 + warp] = rbf(1.f - gt);
        }
    }

    {
        uint32_t xb[4][2];
#pragma unroll
        for (int ks = 0; ks < 4; ks++) {
            const __nv_bfloat16* p = xs + (g & 3) * 520 + warp * 64 + ks * 16 + 2 * t4;
            xb[ks][0] = *reinterpret_cast<const uint32_t*>(p);
            xb[ks][1] = *reinterpret_cast<const uint32_t*>(p + 8);
        }
        const int item = warp >> 2;
        mbar_wait(bar_full + item * 8, 0);
        float cq[2][4] = {};
#pragma unroll
        for (int ks = 0; ks < 4; ks++) {
            const int row = (warp & 3) * 64 + ks * 16 + l7 + (mi >> 1) * 8;
#pragma unroll
            for (int mt = 0; mt < 2; mt++) {
                uint32_t a[4];
                const int ch = 2 * mt + (mi & 1);
                ldsm4t(a, sb + item * SLOT + row * 64 + ((ch ^ ((row >> 1) & 3)) << 4));
                mma16816(cq[mt], a, xb[ks][0], xb[ks][1]);
            }
        }
        __syncwarp();
        if (lane == 0) mbar_arrive2(bar_empty + item * 8);
        if (t4 < 2) {
#pragma unroll
            for (int mt = 0; mt < 2; mt++) {
                float* r = red + warp * 128 + (2 * t4) * 32 + mt * 16 + g;
                r[0] = cq[mt][0]; r[32] = cq[mt][1]; r[8] = cq[mt][2]; r[40] = cq[mt][3];
            }
        }
        bar_sync(1, 256);
    }
    if (warp < 4) {
        float s = 0.f;
#pragma unroll
        for (int w = 0; w < 8; w++) s += red[w * 128 + tid];
        st_rlx_u32(&g_q[warp * 4096 + c * 32 + lane], (pack_bf16(0.f, s) & 0xffff0000u) | tag);
        if (tid == 0) *cnt = 0;
    }
    bar_sync(1, 256);

    const int wg = warp >> 2;
    const uint32_t koff = ((warp & 3) * 16 + l7 + (mi & 1) * 8) * 128;
    const uint32_t voff = (warp >> 2) * 8192 + (l7 + (mi >> 1) * 8) * 128 + (((2 * (warp & 3) + (mi & 1)) ^ l7) << 4);
    const float SC = 0.08838834764831845f;
    const int cons = (t4 & 1) * 8 + warp;
    float* const pf = xg + X_PF + (grp * 16 + cons) * XF_STRIDE + (jj >> 5) * 2048 + (t4 >> 1) * 1024 + (jj & 31) * 32 + g * 4;
    float* const po = g_po + ((size_t)cons * G + jj) * 32 + g * 4;

#pragma unroll 1
    for (int ph = -1; ph < NPH; ph++) {
        const bool last = ph == NPH - 1;
        if (!last) {
            const int pk = ph + 1, P = pk * NG + grp;
            mbar_wait(sb + OFF_QBAR + pk * 8, 0);
            uint32_t qf[8][2];
#pragma unroll
            for (int kk = 0; kk < 8; kk++) {
                const unsigned char* p = sg + OFF_QS + ((pk * 4 + (g & 3)) * 136 + kk * 16 + 2 * t4) * 2;
                qf[kk][0] = *reinterpret_cast<const uint32_t*>(p);
                qf[kk][1] = *reinterpret_cast<const uint32_t*>(p + 16);
            }
            uint32_t ua[TPG], ub[TPG];
            float mx0 = -INFINITY, mx1 = -INFINITY;
            const int itp = it_kv0 + max(0, 2 * pk - 1) * TP + wg;
#pragma unroll
            for (int i = 0; i < TPG; i++) {
                const int it = itp + 2 * i, sk = it % NS;
                mbar_wait(bar_full + sk * 8, (it / NS) & 1);
                float sa[4] = {0.f, 0.f, 0.f, 0.f}, sc[4] = {0.f, 0.f, 0.f, 0.f};
                const uint32_t kb = sb + sk * SLOT + koff;
#pragma unroll
                for (int kk = 0; kk < 4; kk++) {
                    uint32_t a[4], a2[4];
                    const uint32_t sw = ((2 * kk + (mi >> 1)) ^ l7) << 4;
                    ldsm4(a, kb + sw);
                    ldsm4(a2, kb + 8192 + sw);
                    mma16816(sa, a, qf[kk][0], qf[kk][1]);
                    mma16816(sc, a2, qf[kk + 4][0], qf[kk + 4][1]);
                }
                __syncwarp();
                if (lane == 0) mbar_arrive2(bar_empty + sk * 8);
                const uint32_t ra = pack_bf16(sa[0] + sc[0], sa[1] + sc[1]);
                const uint32_t rb = pack_bf16(sa[2] + sc[2], sa[3] + sc[3]);
                ua[i] = pack_bf16(bf_lo(ra) * SC, bf_hi(ra) * SC);
                ub[i] = pack_bf16(bf_lo(rb) * SC, bf_hi(rb) * SC);
                mx0 = fmaxf(mx0, fmaxf(bf_lo(ua[i]), bf_lo(ub[i])));
                mx1 = fmaxf(mx1, fmaxf(bf_hi(ua[i]), bf_hi(ub[i])));
            }
#pragma unroll
            for (int o = 4; o <= 16; o <<= 1) {
                mx0 = fmaxf(mx0, __shfl_xor_sync(0xffffffffu, mx0, o));
                mx1 = fmaxf(mx1, __shfl_xor_sync(0xffffffffu, mx1, o));
            }
            float* mb = reinterpret_cast<float*>(sg + OFF_MB) + (pk & 1) * 32;
            if (lane < 2) *reinterpret_cast<float2*>(mb + warp * 4 + 2 * lane) = make_float2(mx0, mx1);
            bar_sync(1, 256);
            float M0 = -INFINITY, M1 = -INFINITY;
#pragma unroll
            for (int w = 0; w < 8; w++) {
                const float2 v = *reinterpret_cast<const float2*>(mb + w * 4 + 2 * (t4 & 1));
                M0 = fmaxf(M0, v.x); M1 = fmaxf(M1, v.y);
            }
            float l0 = 0.f, l1 = 0.f;
#pragma unroll
            for (int i = 0; i < TPG; i++) {
                const uint32_t pa = pack_bf16(ex2((bf_lo(ua[i]) - M0) * L2E), ex2((bf_hi(ua[i]) - M1) * L2E));
                const uint32_t pb = pack_bf16(ex2((bf_lo(ub[i]) - M0) * L2E), ex2((bf_hi(ub[i]) - M1) * L2E));
                l0 += bf_lo(pa) + bf_lo(pb);
                l1 += bf_hi(pa) + bf_hi(pb);
                reinterpret_cast<uint2*>(sg + OFF_PB)[(((pk & 1) * TP + 2 * i + wg) * 4 + (warp & 3)) * 32 + lane] =
                    make_uint2(movmatrix_t(pa), movmatrix_t(pb));
            }
#pragma unroll
            for (int o = 4; o <= 16; o <<= 1) {
                l0 += __shfl_xor_sync(0xffffffffu, l0, o);
                l1 += __shfl_xor_sync(0xffffffffu, l1, o);
            }
            float* lb = reinterpret_cast<float*>(sg + OFF_LB);
            if (lane < 2) *reinterpret_cast<float2*>(lb + warp * 4 + 2 * lane) = make_float2(l0, l1);
            if (warp < 7) {
                bar_arrive(3, 256);
            } else {
                bar_sync(3, 256);
                const int hp = lane >> 4;
                float s0 = 0.f, s1 = 0.f;
#pragma unroll
                for (int w = 0; w < 8; w++) { const float2 v = *reinterpret_cast<const float2*>(lb + w * 4 + 2 * hp); s0 += v.x; s1 += v.y; }
                const float ma = __shfl_sync(0xffffffffu, M0, hp), mc = __shfl_sync(0xffffffffu, M1, hp);
                const uint32_t w0 = tagf(ma, tag), w1 = tagf(s0, tag), w2 = tagf(mc, tag), w3 = tagf(s1, tag);
                float* mf = xg + X_MF + (grp * 16 + (lane >> 1)) * 2048 + jj * 8 + (lane & 1) * 4;
                if (pk == NPH - 1) {
                    st_rlx_v4(mf, w0, w1, w2, w3);
                    st_rlx_v4(mf + 1024, w0, w1, w2, w3);
                } else if ((lane & 15) == 0) {
                    st_rlx_v4(g_ml + (P * G + jj) * 8 + hp * 4, w0, w1, w2, w3);
                }
                if (pk == REH) {
                    st_rlx_v4(mf, 0u, 0u, 0u, 0u);
                    st_rlx_v4(mf + 1024, 0u, 0u, 0u, 0u);
                    if ((lane & 15) == 0) st_rlx_v4(g_ml + (((NPH - 2) * NG + grp) * G + jj) * 8 + hp * 4, 0u, 0u, 0u, 0u);
                }
            }
        } else {
            bar_sync(1, 256);
        }
        if (ph >= 0) {
            const int P = ph * NG + grp;
            const int itp = it_kv0 + min(2 * ph + 2, 2 * NPH - 1) * TP;
            float acc[4] = {0.f, 0.f, 0.f, 0.f}, acd[4] = {0.f, 0.f, 0.f, 0.f};
#pragma unroll
            for (int i = 0; i < TP; i++) {
                const int it = itp + i, sv = it % NS;
                uint2 pb[4];
#pragma unroll
                for (int ks = 0; ks < 4; ks++) pb[ks] = reinterpret_cast<const uint2*>(sg + OFF_PB)[(((ph & 1) * TP + i) * 4 + ks) * 32 + lane];
                mbar_wait(bar_full + sv * 8, (it / NS) & 1);
                const uint32_t vb = sb + sv * SLOT + voff;
                uint32_t a[4][4];
#pragma unroll
                for (int ks = 0; ks < 4; ks++) ldsm4t(a[ks], vb + ks * 2048);
                mma16816(acc, a[0], pb[0].x, pb[0].y);
                mma16816(acd, a[1], pb[1].x, pb[1].y);
                mma16816(acc, a[2], pb[2].x, pb[2].y);
                mma16816(acd, a[3], pb[3].x, pb[3].y);
                if (i + 1 < TP || !last) {
                    __syncwarp();
                    if (lane == 0) mbar_arrive(bar_empty + sv * 8);
                }
            }
            const uint32_t w0 = tagf(acc[0] + acd[0], tag), w1 = tagf(acc[1] + acd[1], tag);
            const uint32_t w2 = tagf(acc[2] + acd[2], tag), w3 = tagf(acc[3] + acd[3], tag);
            st_rlx_v4_if(last ? pf : po + (size_t)P * (16 * G * 32), w0, w1, w2, w3, last || t4 < 2);
            if (tid == 224) *cnt = last ? NPH + 1 : ph + 1;
            if (ph == REH - 1 && warp < 4)
                st_rlx_v4(xg + X_P2 + ((c & 7) + 8 * (tid >> 3)) * 4096 + (c >> 6) * 2048 + ((tid >> 2) & 1) * 1024 + (c & 63) * 16 + (tid & 3) * 4,
                          0u, 0u, 0u, 0u);
            if (ph == REH) st_rlx_v4(pf, 0u, 0u, 0u, 0u);
            if (ph == REH + 1 && t4 < 2) st_rlx_v4(po + (size_t)((NPH - 2) * NG + grp) * (16 * G * 32), 0u, 0u, 0u, 0u);
        }

        if (!(last || ph == REH)) continue;
        const uint32_t ptag = last ? tag : 0u;
        if (has_glu) {
            float cg[4] = {0.f, 0.f, 0.f, 0.f}, cu[4] = {0.f, 0.f, 0.f, 0.f};
            uint32_t xb[4][2];
#pragma unroll
            for (int ks = 0; ks < 4; ks++) {
                const __nv_bfloat16* p = xs + (g & 3) * 520 + warp * 64 + ks * 16 + 2 * t4;
                xb[ks][0] = *reinterpret_cast<const uint32_t*>(p);
                xb[ks][1] = *reinterpret_cast<const uint32_t*>(p + 8);
            }
            const int rowb = warp * 64 + l7 + (mi >> 1) * 8;
            const uint32_t aoff = rowb * 32 + (((mi & 1) ^ ((rowb >> 2) & 1)) << 4);
            const int glim = last ? 16 * SPIN_LIMIT : 0;
            mbar_spin(bar_full + (it_g % NS) * 8, (it_g / NS) & 1, glim);
#pragma unroll
            for (int ks = 0; ks < 4; ks++) {
                uint32_t a[4];
                ldsm4t(a, sb + (it_g % NS) * SLOT + aoff + ks * 512);
                mma16816(cg, a, xb[ks][0], xb[ks][1]);
            }
            mbar_spin(bar_full + (it_u % NS) * 8, (it_u / NS) & 1, glim);
#pragma unroll
            for (int ks = 0; ks < 4; ks++) {
                uint32_t a[4];
                ldsm4t(a, sb + (it_u % NS) * SLOT + aoff + ks * 512);
                mma16816(cu, a, xb[ks][0], xb[ks][1]);
            }
            float* red2 = reinterpret_cast<float*>(sg + OFF_RED2);
            if (t4 < 2) {
                float* r = red2 + warp * 128 + (2 * t4) * 16 + g;
                r[0] = cg[0]; r[16] = cg[1]; r[8] = cg[2]; r[24] = cg[3];
                r[64] = cu[0]; r[80] = cu[1]; r[72] = cu[2]; r[88] = cu[3];
            }
            bar_sync(1, 256);
            if (warp < 2) {
                float Gv = 0.f, Uv = 0.f;
#pragma unroll
                for (int w = 0; w < 8; w++) { Gv += red2[w * 128 + tid]; Uv += red2[w * 128 + 64 + tid]; }
                const float h = rbf(sigmoidf(rbf(Gv))) * rbf(Uv);
                reinterpret_cast<__nv_bfloat16*>(sg + OFF_HS)[(tid >> 4) * 24 + (tid & 15)] = __float2bfloat16_rn(h);
            }
            bar_sync(1, 256);
        }
        const bool hi = t4 >= 2;
        const int bo = (2 * t4 + (hi ? 1 : 0)) & 3;
        const float ga = gates[bo], gb = gates[4 + bo];
        const unsigned char* hsp = sg + OFF_HS + ((g & 3) * 24 + 2 * t4) * 2;
        const uint32_t hb0 = *reinterpret_cast<const uint32_t*>(hsp), hb1 = *reinterpret_cast<const uint32_t*>(hsp + 16);
        const uint32_t woff = (warp >> 2) * 2048 + (l7 + (mi >> 1) * 8) * 128 + (((2 * (warp & 3) + (mi & 1)) ^ l7) << 4);
        if (last) bar_sync(5, 320);
        const uint4 ob = reinterpret_cast<const uint4*>(sg + OFF_OS)[(g & 3) * 4 + t4];
        float* dst[4];
        uint64_t h64 = 0;
#pragma unroll
        for (int i = 0; i < 4; i++) {
            const int cd = bo * 32 + ((i + (c >> 5)) & 3) * 8 + warp;
            dst[i] = xg + X_P2 + cd * 4096 + (c >> 6) * 2048 + (c & 63) * 16 + 2 * g +
                     (*reinterpret_cast<const uint32_t*>(sg + OFF_SELP + cd * 4) & 1024u);
            h64 ^= (uintptr_t)dst[i];
        }
        const float* src = xg + X_P2 + c * 4096 + (warp >> 2) * 2048 + (warp & 3) * 256 + lane * 4 +
                           (reinterpret_cast<volatile int*>(sg + OFF_SEL)[warp >> 2] & 1) * 1024;
        h64 ^= (uintptr_t)src;
        const uint32_t hsh = (uint32_t)h64 ^ (uint32_t)(h64 >> 32) ^ __float_as_uint(ga) ^ __float_as_uint(gb) ^ hb0 ^ hb1 ^ ob.x ^ ob.z;
        const int lim = last ? 16 * SPIN_LIMIT + (hsh == 0x9e3779b9u) : 0;
#pragma unroll
        for (int i = 0; i < 4; i++) {
            const int it = it_tail + i;
            mbar_spin(bar_full + (it % NS) * 8, (it / NS) & 1, lim);
            uint32_t wa[3][4];
#pragma unroll
            for (int ks = 0; ks < 3; ks++) ldsm4t(wa[ks], sb + (it % NS) * SLOT + ks * 4096 + woff);
            float ca[4] = {0.f, 0.f, 0.f, 0.f}, cc[4] = {0.f, 0.f, 0.f, 0.f}, cb[4] = {0.f, 0.f, 0.f, 0.f};
            mma16816(ca, wa[0], ob.x, ob.y);
            mma16816(cc, wa[1], ob.z, ob.w);
            if (has_glu) mma16816(cb, wa[2], hb0, hb1);
            const float v0 = fmaf(ga, hi ? ca[1] + cc[1] : ca[0] + cc[0], gb * (hi ? cb[1] : cb[0]));
            const float v1 = fmaf(ga, hi ? ca[3] + cc[3] : ca[2] + cc[2], gb * (hi ? cb[3] : cb[2]));
            st_rlx_v2_if(dst[i], tagf(v0, ptag), tagf(v1, ptag), last);
        }

        float a0, a1, a2, a3;
        {
            uint4 v0 = make_uint4(0u, 0u, 0u, 0u), v1 = v0;
            bool p0 = last, p1 = last;
            for (int n = 0; n < SPIN_LIMIT; n++) {
                ld_rlx_v4_if(v0, src, p0);
                ld_rlx_v4_if(v1, src + 128, p1);
                p0 = !ok4(v0, ptag, 3u);
                p1 = !ok4(v1, ptag, 3u);
                if (!__any_sync(0xffffffffu, p0 | p1)) break;
            }
            a0 = untag(v0.x) + untag(v1.x); a1 = untag(v0.y) + untag(v1.y);
            a2 = untag(v0.z) + untag(v1.z); a3 = untag(v0.w) + untag(v1.w);
        }
#pragma unroll
        for (int o = 4; o <= 16; o <<= 1) {
            a0 += __shfl_xor_sync(0xffffffffu, a0, o); a1 += __shfl_xor_sync(0xffffffffu, a1, o);
            a2 += __shfl_xor_sync(0xffffffffu, a2, o); a3 += __shfl_xor_sync(0xffffffffu, a3, o);
        }
        float* fin = reinterpret_cast<float*>(sg + OFF_FIN);
        if (lane < 4) *reinterpret_cast<float4*>(fin + warp * 16 + lane * 4) = make_float4(a0, a1, a2, a3);
        bar_sync(1, 256);
        if (tid < 16) {
            const float s = ((fin[tid] + fin[16 + tid]) + (fin[32 + tid] + fin[48 + tid])) +
                            ((fin[64 + tid] + fin[80 + tid]) + (fin[96 + tid] + fin[112 + tid]));
            asm volatile("{\n.reg .pred p;\nsetp.ne.u32 p, %2, 0;\n@p st.global.u16 [%0], %1;\n}\n"
                         :: "l"(out + (c >> 5) * 512 + (c & 31) * 16 + (tid >> 1) + 8 * (tid & 1)),
                            "h"((unsigned short)pack_bf16(s, 0.f)), "r"((uint32_t)last) : "memory");
            if (last && c == 0 && tid == 0) st_rlx_u32(&g_epoch, epoch + 1u);
        }
    }
}

typedef CUresult (*EncodeFn)(CUtensorMap*, CUtensorMapDataType, cuuint32_t, void*, const cuuint64_t*, const cuuint64_t*,
                             const cuuint32_t*, const cuuint32_t*, CUtensorMapInterleave, CUtensorMapSwizzle,
                             CUtensorMapL2promotion, CUtensorMapFloatOOBfill);

void make_map(EncodeFn enc, CUtensorMap* m, const void* p, int rank, const cuuint64_t* gd, const cuuint64_t* gs,
              const cuuint32_t* bd, CUtensorMapSwizzle sw,
              CUtensorMapL2promotion prom = CU_TENSOR_MAP_L2_PROMOTION_L2_256B) {
    const cuuint32_t es[3] = {1, 1, 1};
    enc(m, CU_TENSOR_MAP_DATA_TYPE_BFLOAT16, (cuuint32_t)rank, const_cast<void*>(p), gd, gs, bd, es,
        CU_TENSOR_MAP_INTERLEAVE_NONE, sw, prom, CU_TENSOR_MAP_FLOAT_OOB_FILL_NONE);
}

}

extern "C" void kernel_launch(void* const* d_in, const int* in_sizes, int n_in, void* d_out, int out_size) {
    (void)in_sizes; (void)n_in; (void)out_size;
    static EncodeFn enc = nullptr;
    static int tau = TAU;
    if (!enc) {
        void* fn = nullptr;
        cudaDriverEntryPointQueryResult qr;
        cudaGetDriverEntryPoint("cuTensorMapEncodeTiled", &fn, cudaEnableDefault, &qr);
        enc = (EncodeFn)fn;
        cudaFuncSetAttribute(fused_decode_kernel, cudaFuncAttributeMaxDynamicSharedMemorySize, SMEM_BYTES);
        int dev = 0, khz = 0, bits = 0;
        cudaGetDevice(&dev);
        cudaDeviceGetAttribute(&khz, cudaDevAttrMemoryClockRate, dev);
        cudaDeviceGetAttribute(&bits, cudaDevAttrGlobalMemoryBusWidth, dev);
        if (khz > 0 && bits > 0) tau = (int)(TAU * (2619000.0 * 5120.0) / ((double)khz * bits) + 0.5);
    }
    Maps maps;
    {
        const cuuint64_t gd[3] = {64, 262144, 2}, gs[2] = {256, 128};
        const cuuint32_t bd[3] = {64, 64, 2};
        make_map(enc, &maps.k, d_in[1], 3, gd, gs, bd, CU_TENSOR_MAP_SWIZZLE_128B);
        make_map(enc, &maps.v, d_in[2], 3, gd, gs, bd, CU_TENSOR_MAP_SWIZZLE_128B);
    }
    {
        const cuuint64_t gd[2] = {4096, 512}, gs[1] = {8192};
        const cuuint32_t bd[2] = {32, 256};
        make_map(enc, &maps.wq, d_in[3], 2, gd, gs, bd, CU_TENSOR_MAP_SWIZZLE_64B);
    }
    {
        const cuuint64_t gd[2] = {1792, 512}, gs[1] = {3584};
        const cuuint32_t bd[2] = {16, 256};
        make_map(enc, &maps.wg, d_in[6], 2, gd, gs, bd, CU_TENSOR_MAP_SWIZZLE_32B, CU_TENSOR_MAP_L2_PROMOTION_L2_128B);
        make_map(enc, &maps.wu, d_in[7], 2, gd, gs, bd, CU_TENSOR_MAP_SWIZZLE_32B, CU_TENSOR_MAP_L2_PROMOTION_L2_128B);
    }
    {
        const cuuint64_t gdo[3] = {64, 4096, 8}, gdd[3] = {64, 1792, 8}, gs[2] = {1024, 128};
        const cuuint32_t bd[3] = {64, 16, 2};
        make_map(enc, &maps.wo, d_in[4], 3, gdo, gs, bd, CU_TENSOR_MAP_SWIZZLE_128B);
        make_map(enc, &maps.wd, d_in[8], 3, gdd, gs, bd, CU_TENSOR_MAP_SWIZZLE_128B);
    }
    fused_decode_kernel<<<NCTA, NTHREADS, SMEM_BYTES, cudaStreamPerThread>>>(
        maps, (const __nv_bfloat16*)d_in[0], (const __nv_bfloat16*)d_in[9], (const __nv_bfloat16*)d_in[3], (__nv_bfloat16*)d_out, tau);
}
```
